```python
import torch

def _softmax(x, axis=-1):
    return torch.softmax(x, dim=axis)
def _gelu(x):
    return torch.nn.functional.gelu(x, approximate="tanh")
def _silu(x):
    return torch.nn.functional.silu(x)
def _sigmoid(x):
    return torch.sigmoid(x)
def _layernorm(x, axis=-1, eps=1e-5):
    m = x.mean(dim=axis, keepdim=True)
    v = x.var(dim=axis, keepdim=True, unbiased=False)
    return (x - m) / torch.sqrt(v + eps)
def _scatter_add(tgt, idx, src, axis=0):
    return tgt.clone().index_add_(axis, idx, src)
def _segment_sum(src, seg, n):
    out = torch.zeros((n,) + src.shape[1:], dtype=src.dtype)
    return out.index_add_(0, seg, src)
def _pad(x, pw):
    flat = tuple(v for pair in reversed(pw) for v in pair)
    return torch.nn.functional.pad(x, flat)

kernel_name = 'standalone__sliding_block_cached__sampling'

def setup_inputs():

    _w = (lambda a: (lambda t: t.to(torch.bfloat16) if t.is_floating_point() else t)(torch.as_tensor(a)))
    B, Sq, D = 8, 32, 512
    Hq, Hkv, Sk, Dh = 32, 8, 8192, 128
    assert Hq % Hkv == 0, (Hq, Hkv)
    return {
        "x": _w((lambda *s: torch.randn(*s, dtype=torch.bfloat16) * 0.8)(B, Sq, D)),
        "k_cache": _w((lambda *s: torch.randn(*s, dtype=torch.bfloat16) * 0.8)(B, Hkv, Sk, Dh)),
        "v_cache": _w((lambda *s: torch.randn(*s, dtype=torch.bfloat16) * 0.05)(B, Hkv, Sk, Dh)),
        "wq": _w((lambda *s: torch.randn(*s, dtype=torch.bfloat16) * 0.8)(D, Hq * Dh) * (D ** -0.5)),
        "wo": _w((lambda *s: torch.randn(*s, dtype=torch.bfloat16) * 0.05)(Hq * Dh, D) * ((Hq * Dh) ** -0.5)),
    }

def reference(x, k_cache, v_cache, wq, wo):
    B, Sq, D = x.shape
    Hq, Dh = 32, 128
    Hkv, Sk = k_cache.shape[1], k_cache.shape[2]
    W = min(4096, max(256, Sk // 4))
    rep = Hq // Hkv
    q = (lambda x, *d: x.permute(*d))((x @ wq).reshape(B, Sq, Hq, Dh), 0, 2, 1, 3)
    k = (lambda x, n, axis: torch.repeat_interleave(x, n, dim=axis))(k_cache[:, :, Sk - W:, :], rep, axis=1)
    v = (lambda x, n, axis: torch.repeat_interleave(x, n, dim=axis))(v_cache[:, :, Sk - W:, :], rep, axis=1)
    scores = torch.einsum("bhqd,bhkd->bhqk", q, k) * (Dh ** -0.5)
    p = _softmax(scores, axis=-1)
    o = torch.einsum("bhqk,bhkd->bhqd", p, v)
    return (lambda x, *d: x.permute(*d))(o, 0, 2, 1, 3).reshape(B, Sq, Hq * Dh) @ wo
```

```cpp
#include <cuda_runtime.h>
#include <cuda_bf16.h>
#include <cuda.h>
#include <stdint.h>

namespace sbk {

constexpr int NB = 8, SQ = 32, DM = 512, HQ = 32, HKV = 8, SK = 8192, DH = 128, WIN = 2048;
constexpr int NT = WIN / 128;
constexpr uint32_t SLOT = 32768;
constexpr uint32_t OFF_AUX = 6 * SLOT;
constexpr uint32_t OFF_Q = OFF_AUX;
constexpr uint32_t OFF_O = OFF_AUX + 16384;
constexpr uint32_t OFF_MISC = OFF_AUX + 32768;
constexpr uint32_t OFF_FULL = OFF_MISC;
constexpr uint32_t OFF_EMPTY = OFF_MISC + 384;
constexpr uint32_t OFF_XFULL = OFF_MISC + 768;
constexpr uint32_t OFF_STATS = OFF_MISC + 1024;
constexpr uint32_t SMEM_BYTES = OFF_MISC + 3072;
constexpr int U_WQ = 0, U_KV = 8, U_WO = 40, N_USE = 48;
constexpr int NTHREADS = 288;
constexpr int SPIN_LIMIT = 1 << 24;

__device__ unsigned int g_zero_cnt[NB * 32];

__device__ __forceinline__ void mbar_init(uint32_t bar, uint32_t cnt) {
  asm volatile("mbarrier.init.shared::cta.b64 [%0], %1;" ::"r"(bar), "r"(cnt) : "memory");
}
__device__ __forceinline__ void mbar_expect_tx(uint32_t bar, uint32_t bytes) {
  asm volatile("mbarrier.arrive.expect_tx.shared::cta.b64 _, [%0], %1;" ::"r"(bar), "r"(bytes) : "memory");
}
__device__ __forceinline__ void mbar_arrive(uint32_t bar) {
  asm volatile("mbarrier.arrive.shared::cta.b64 _, [%0];" ::"r"(bar) : "memory");
}
__device__ __forceinline__ bool mbar_try0(uint32_t bar) {
  uint32_t ok;
  asm volatile("{\n.reg .pred p;\nmbarrier.try_wait.parity.shared::cta.b64 p, [%1], 0;\nselp.u32 %0,1,0,p;\n}"
               : "=r"(ok) : "r"(bar) : "memory");
  return ok;
}
__device__ __forceinline__ void mbar_wait0(uint32_t bar) {
  int it = 0;
  while (!mbar_try0(bar)) { if (++it > SPIN_LIMIT) __trap(); }
}
__device__ __forceinline__ void tma3d(uint32_t dst, const CUtensorMap* m, int c0, int c1, int c2, uint32_t bar) {
  asm volatile("cp.async.bulk.tensor.3d.shared::cluster.global.mbarrier::complete_tx::bytes [%0], [%1, {%3, %4, %5}], [%2];"
               ::"r"(dst), "l"(m), "r"(bar), "r"(c0), "r"(c1), "r"(c2) : "memory");
}
__device__ __forceinline__ void tma_reduce2d(const CUtensorMap* m, int c0, int c1, uint32_t src) {
  asm volatile("cp.reduce.async.bulk.tensor.2d.global.shared::cta.add.tile.bulk_group [%0, {%2, %3}], [%1];"
               ::"l"(m), "r"(src), "r"(c0), "r"(c1) : "memory");
}
__device__ __forceinline__ void prefetch_map(const CUtensorMap* m) {
  asm volatile("prefetch.tensormap [%0];" ::"l"(m) : "memory");
}
__device__ __forceinline__ void bar_sync(int id, int n) { asm volatile("bar.sync %0, %1;" ::"r"(id), "r"(n) : "memory"); }
__device__ __forceinline__ void bar_arrive(int id, int n) { asm volatile("bar.arrive %0, %1;" ::"r"(id), "r"(n) : "memory"); }
__device__ __forceinline__ void fence_async_smem() { asm volatile("fence.proxy.async.shared::cta;" ::: "memory"); }
__device__ __forceinline__ void fence_async_all() { asm volatile("fence.proxy.async;" ::: "memory"); }
__device__ __forceinline__ void wg_fence() { asm volatile("wgmma.fence.sync.aligned;" ::: "memory"); }
__device__ __forceinline__ void wg_commit() { asm volatile("wgmma.commit_group.sync.aligned;" ::: "memory"); }
template <int N> __device__ __forceinline__ void wg_wait() { asm volatile("wgmma.wait_group.sync.aligned %0;" ::"n"(N) : "memory"); }
template <int N> __device__ __forceinline__ void reg_fence(float (&d)[N]) {
#pragma unroll
  for (int i = 0; i < N; i++) asm volatile("" : "+f"(d[i])::"memory");
}
__device__ __forceinline__ uint64_t mkdesc(uint32_t addr, uint32_t lbo, uint32_t sbo) {
  return (uint64_t)((addr >> 4) & 0x3FFF) | ((uint64_t)(lbo >> 4) << 16) | ((uint64_t)(sbo >> 4) << 32) | (1ull << 62);
}
__device__ __forceinline__ float ex2(float x) { float y; asm("ex2.approx.ftz.f32 %0, %1;" : "=f"(y) : "f"(x)); return y; }
__device__ __forceinline__ uint32_t pack_bf16(float lo, float hi) {
  uint32_t r; asm("cvt.rn.bf16x2.f32 %0, %1, %2;" : "=r"(r) : "f"(hi), "f"(lo)); return r;
}
__device__ __forceinline__ void stsm4(uint32_t addr, uint32_t a, uint32_t b, uint32_t c, uint32_t d) {
  asm volatile("stmatrix.sync.aligned.m8n8.x4.shared.b16 [%0], {%1,%2,%3,%4};" ::"r"(addr), "r"(a), "r"(b), "r"(c), "r"(d) : "memory");
}
__device__ __forceinline__ void stsm4t(uint32_t addr, uint32_t a, uint32_t b, uint32_t c, uint32_t d) {
  asm volatile("stmatrix.sync.aligned.m8n8.x4.trans.shared.b16 [%0], {%1,%2,%3,%4};" ::"r"(addr), "r"(a), "r"(b), "r"(c), "r"(d) : "memory");
}

#define ACC16(d) "+f"(d[0]), "+f"(d[1]), "+f"(d[2]), "+f"(d[3]), "+f"(d[4]), "+f"(d[5]), "+f"(d[6]), "+f"(d[7]), \
                 "+f"(d[8]), "+f"(d[9]), "+f"(d[10]), "+f"(d[11]), "+f"(d[12]), "+f"(d[13]), "+f"(d[14]), "+f"(d[15])
#define ACC64(d) ACC16(d), \
  "+f"(d[16]), "+f"(d[17]), "+f"(d[18]), "+f"(d[19]), "+f"(d[20]), "+f"(d[21]), "+f"(d[22]), "+f"(d[23]), \
  "+f"(d[24]), "+f"(d[25]), "+f"(d[26]), "+f"(d[27]), "+f"(d[28]), "+f"(d[29]), "+f"(d[30]), "+f"(d[31]), \
  "+f"(d[32]), "+f"(d[33]), "+f"(d[34]), "+f"(d[35]), "+f"(d[36]), "+f"(d[37]), "+f"(d[38]), "+f"(d[39]), \
  "+f"(d[40]), "+f"(d[41]), "+f"(d[42]), "+f"(d[43]), "+f"(d[44]), "+f"(d[45]), "+f"(d[46]), "+f"(d[47]), \
  "+f"(d[48]), "+f"(d[49]), "+f"(d[50]), "+f"(d[51]), "+f"(d[52]), "+f"(d[53]), "+f"(d[54]), "+f"(d[55]), \
  "+f"(d[56]), "+f"(d[57]), "+f"(d[58]), "+f"(d[59]), "+f"(d[60]), "+f"(d[61]), "+f"(d[62]), "+f"(d[63])
#define REGS16 "{%0,%1,%2,%3,%4,%5,%6,%7,%8,%9,%10,%11,%12,%13,%14,%15}"
#define REGS64 "{%0,%1,%2,%3,%4,%5,%6,%7,%8,%9,%10,%11,%12,%13,%14,%15,%16,%17,%18,%19,%20,%21,%22,%23,%24,%25,%26,%27,%28,%29,%30,%31," \
               "%32,%33,%34,%35,%36,%37,%38,%39,%40,%41,%42,%43,%44,%45,%46,%47,%48,%49,%50,%51,%52,%53,%54,%55,%56,%57,%58,%59,%60,%61,%62,%63}"

__device__ __forceinline__ void wgmma_n32_tA(float (&d)[16], uint64_t da, uint64_t db, int acc) {
  asm volatile("{\n.reg .pred p;\nsetp.ne.b32 p, %18, 0;\n"
               "wgmma.mma_async.sync.aligned.m64n32k16.f32.bf16.bf16 " REGS16 ", %16, %17, p, 1, 1, 1, 0;\n}"
               : ACC16(d) : "l"(da), "l"(db), "r"(acc));
}
__device__ __forceinline__ void wgmma_n128_ss(float (&d)[64], uint64_t da, uint64_t db, int acc) {
  asm volatile("{\n.reg .pred p;\nsetp.ne.b32 p, %66, 0;\n"
               "wgmma.mma_async.sync.aligned.m64n128k16.f32.bf16.bf16 " REGS64 ", %64, %65, p, 1, 1, 0, 0;\n}"
               : ACC64(d) : "l"(da), "l"(db), "r"(acc));
}
__device__ __forceinline__ void wgmma_n128_rs_tB(float (&d)[64], uint32_t a0, uint32_t a1, uint32_t a2, uint32_t a3, uint64_t db) {
  asm volatile("{\n.reg .pred p;\nsetp.ne.b32 p, 1, 0;\n"
               "wgmma.mma_async.sync.aligned.m64n128k16.f32.bf16.bf16 " REGS64 ", {%64,%65,%66,%67}, %68, p, 1, 1, 1;\n}"
               : ACC64(d) : "r"(a0), "r"(a1), "r"(a2), "r"(a3), "l"(db));
}

__device__ __forceinline__ uint32_t kv_slot(int i) { return (uint32_t)((i + 4) % 6); }

__global__ void __cluster_dims__(2, 1, 1) __launch_bounds__(NTHREADS, 1)
fused_kernel(const __grid_constant__ CUtensorMap map_x, const __grid_constant__ CUtensorMap map_wq,
             const __grid_constant__ CUtensorMap map_k, const __grid_constant__ CUtensorMap map_v,
             const __grid_constant__ CUtensorMap map_wo, const __grid_constant__ CUtensorMap map_out,
             __nv_bfloat16* __restrict__ out) {
  extern __shared__ __align__(1024) unsigned char smem_raw[];
  const uint32_t sb = (uint32_t)__cvta_generic_to_shared(smem_raw);
  const int tid = threadIdx.x, warp = tid >> 5, lane = tid & 31;
  const int cl = blockIdx.x >> 1, r = blockIdx.x & 1;
  const int hkv = cl & 7, b = cl >> 3;
  const int head0 = 4 * hkv + 2 * r;

  if (tid < 2 * N_USE + 1) {
    uint32_t cnt = 1;
    if (tid >= N_USE && tid < 2 * N_USE) {
      const int u = tid - N_USE;
      cnt = (u >= U_KV && u < U_WO) ? 4 : 8;
    }
    mbar_init(sb + OFF_MISC + tid * 8, cnt);
    asm volatile("fence.mbarrier_init.release.cluster;" ::: "memory");
  }
  if (tid == 0 && (sb & 1023)) __trap();
  __syncthreads();

  if (warp == 8) {
    if (lane == 0) {
      const int kvrow = (b * HKV + hkv) * SK + (SK - WIN);
      auto load_wq = [&](int kc) {
        const uint32_t bar = sb + OFF_FULL + (U_WQ + kc) * 8;
        mbar_expect_tx(bar, SLOT);
        tma3d(sb + (kc & 3) * SLOT, &map_wq, 0, kc * 64, head0 * 2, bar);
      };
      auto load_kv = [&](int i) {
        const uint32_t bar = sb + OFF_FULL + (U_KV + i) * 8;
        mbar_expect_tx(bar, SLOT);
        tma3d(sb + kv_slot(i) * SLOT, (i & 1) ? &map_v : &map_k, 0, kvrow + (i >> 1) * 128, 0, bar);
      };
      mbar_expect_tx(sb + OFF_XFULL, 32768);
      tma3d(sb + OFF_AUX, &map_x, 0, b * SQ, 0, sb + OFF_XFULL);
      for (int kc = 0; kc < 4; kc++) load_wq(kc);
      load_kv(0);
      load_kv(1);
      for (int kc = 4; kc < 8; kc++) { mbar_wait0(sb + OFF_EMPTY + (U_WQ + kc - 4) * 8); load_wq(kc); }
      for (int i = 2; i < 2 * NT; i++) {
        const int prev = i < 6 ? (U_WQ + i + 2) : (U_KV + i - 6);
        mbar_wait0(sb + OFF_EMPTY + prev * 8);
        load_kv(i);
      }
      for (int c = 0; c < 8; c++) {
        const int prev = c < 6 ? (U_KV + 26 + c) : (U_WO + c - 6);
        mbar_wait0(sb + OFF_EMPTY + prev * 8);
        const uint32_t bar = sb + OFF_FULL + (U_WO + c) * 8;
        mbar_expect_tx(bar, SLOT);
        tma3d(sb + (c % 6) * SLOT, &map_wo, 0, (head0 + (c & 1)) * DH, (c >> 1) * 2, bar);
      }
    }
  } else {
    const int w = warp >> 2, wi = warp & 3, t = tid & 127;
    const int i8 = lane & 7, mi = lane >> 3;

    {
      float qa[2][16];
      mbar_wait0(sb + OFF_XFULL);
#pragma unroll 1
      for (int kc = 0; kc < 8; kc++) {
        mbar_wait0(sb + OFF_FULL + (U_WQ + kc) * 8);
        const uint64_t da = mkdesc(sb + (kc & 3) * SLOT + 2 * w * 8192, 16, 1024);
        const uint64_t db = mkdesc(sb + OFF_AUX + kc * 4096, 16, 1024);
        wg_fence();
#pragma unroll
        for (int mt = 0; mt < 2; mt++)
#pragma unroll
          for (int ks = 0; ks < 4; ks++)
            wgmma_n32_tA(qa[mt], da + ((mt * 8192 + ks * 2048) >> 4), db + ((ks * 32) >> 4), (kc | ks) != 0);
        wg_commit();
        wg_wait<0>();
        if (lane == 0) mbar_arrive(sb + OFF_EMPTY + (U_WQ + kc) * 8);
      }
      reg_fence(qa[0]); reg_fence(qa[1]);
      bar_sync(1, 256);
#pragma unroll
      for (int mt = 0; mt < 2; mt++)
#pragma unroll
        for (int jj = 0; jj < 2; jj++) {
          const int j = 2 * jj + (mi >> 1), c16 = 2 * wi + (mi & 1);
          const uint32_t addr = sb + OFF_Q + mt * 8192 + (32 * w + 8 * j + i8) * 128 + ((c16 ^ i8) << 4);
          stsm4t(addr, pack_bf16(qa[mt][8 * jj + 0], qa[mt][8 * jj + 1]), pack_bf16(qa[mt][8 * jj + 2], qa[mt][8 * jj + 3]),
                 pack_bf16(qa[mt][8 * jj + 4], qa[mt][8 * jj + 5]), pack_bf16(qa[mt][8 * jj + 6], qa[mt][8 * jj + 7]));
        }
      fence_async_smem();
      bar_sync(1, 256);
    }

    const float cs = 0.08838834764831845f * 1.4426950408889634f;
    float o[64];
#pragma unroll
    for (int i = 0; i < 64; i++) o[i] = 0.f;
    float m0 = -INFINITY, m1 = -INFINITY, l0 = 0.f, l1 = 0.f;
    unsigned int zero_target = 0;
    const int ntile = w == 0 ? 9 : 7;
#pragma unroll 1
    for (int it = 0; it < ntile; it++) {
      const int j = (it == 8) ? 15 : 2 * it + w;
      const bool last = (j == NT - 1);
      if (last) {
        bar_sync(2, 256);
        const float4 st = *reinterpret_cast<const float4*>(smem_raw + OFF_STATS + t * 16);
        const float n0 = fmaxf(m0, st.x), n1 = fmaxf(m1, st.y);
        const float a0 = ex2((m0 - n0) * cs), a1 = ex2((m1 - n1) * cs);
        const float b0 = ex2((st.x - n0) * cs), b1 = ex2((st.y - n1) * cs);
        m0 = n0; m1 = n1;
        l0 = l0 * a0 + st.z * b0; l1 = l1 * a1 + st.w * b1;
        const float4* dump = reinterpret_cast<const float4*>(smem_raw + kv_slot(27) * SLOT);
#pragma unroll
        for (int i = 0; i < 16; i++) {
          const float4 v = dump[i * 128 + t];
          o[4 * i + 0] = o[4 * i + 0] * a0 + v.x * b0;
          o[4 * i + 1] = o[4 * i + 1] * a0 + v.y * b0;
          o[4 * i + 2] = o[4 * i + 2] * a1 + v.z * b1;
          o[4 * i + 3] = o[4 * i + 3] * a1 + v.w * b1;
        }
        fence_async_all();
        __syncwarp();
        if (lane == 0) mbar_arrive(sb + OFF_EMPTY + (U_KV + 27) * 8);
      }
      float s[64];
      {
        mbar_wait0(sb + OFF_FULL + (U_KV + 2 * j) * 8);
        const uint64_t da = mkdesc(sb + OFF_Q, 16, 1024);
        const uint64_t db = mkdesc(sb + kv_slot(2 * j) * SLOT, 16, 1024);
        wg_fence();
#pragma unroll
        for (int ks = 0; ks < 8; ks++)
          wgmma_n128_ss(s, da + (((ks >> 2) * 8192 + (ks & 3) * 32) >> 4), db + (((ks >> 2) * 16384 + (ks & 3) * 32) >> 4), ks != 0);
        wg_commit();
        wg_wait<0>();
        reg_fence(s);
        if (lane == 0) mbar_arrive(sb + OFF_EMPTY + (U_KV + 2 * j) * 8);
      }
      float x0 = fmaxf(s[0], s[1]), x1 = fmaxf(s[2], s[3]);
#pragma unroll
      for (int i = 1; i < 16; i++) {
        x0 = fmaxf(x0, fmaxf(s[4 * i], s[4 * i + 1]));
        x1 = fmaxf(x1, fmaxf(s[4 * i + 2], s[4 * i + 3]));
      }
      x0 = fmaxf(x0, __shfl_xor_sync(0xffffffffu, x0, 1));
      x1 = fmaxf(x1, __shfl_xor_sync(0xffffffffu, x1, 1));
      x0 = fmaxf(x0, __shfl_xor_sync(0xffffffffu, x0, 2));
      x1 = fmaxf(x1, __shfl_xor_sync(0xffffffffu, x1, 2));
      const float n0 = fmaxf(m0, x0), n1 = fmaxf(m1, x1);
      float a0 = ex2((m0 - n0) * cs), a1 = ex2((m1 - n1) * cs);
      m0 = n0; m1 = n1;
      const float nb0 = -n0 * cs, nb1 = -n1 * cs;
      float r0 = 0.f, r1 = 0.f;
#pragma unroll
      for (int i = 0; i < 16; i++) {
        s[4 * i + 0] = ex2(fmaf(s[4 * i + 0], cs, nb0));
        s[4 * i + 1] = ex2(fmaf(s[4 * i + 1], cs, nb0));
        s[4 * i + 2] = ex2(fmaf(s[4 * i + 2], cs, nb1));
        s[4 * i + 3] = ex2(fmaf(s[4 * i + 3], cs, nb1));
        r0 += s[4 * i] + s[4 * i + 1];
        r1 += s[4 * i + 2] + s[4 * i + 3];
      }
      l0 = l0 * a0 + r0;
      l1 = l1 * a1 + r1;
      if (last) {
        float t0 = l0 + __shfl_xor_sync(0xffffffffu, l0, 1), t1 = l1 + __shfl_xor_sync(0xffffffffu, l1, 1);
        t0 += __shfl_xor_sync(0xffffffffu, t0, 2); t1 += __shfl_xor_sync(0xffffffffu, t1, 2);
        const float i0 = 1.f / t0, i1 = 1.f / t1;
        a0 *= i0; a1 *= i1;
#pragma unroll
        for (int i = 0; i < 16; i++) { s[4 * i] *= i0; s[4 * i + 1] *= i0; s[4 * i + 2] *= i1; s[4 * i + 3] *= i1; }
      }
#pragma unroll
      for (int i = 0; i < 16; i++) { o[4 * i] *= a0; o[4 * i + 1] *= a0; o[4 * i + 2] *= a1; o[4 * i + 3] *= a1; }
      uint32_t p[32];
#pragma unroll
      for (int i = 0; i < 32; i++) p[i] = pack_bf16(s[2 * i], s[2 * i + 1]);
      {
        mbar_wait0(sb + OFF_FULL + (U_KV + 2 * j + 1) * 8);
        const uint64_t db = mkdesc(sb + kv_slot(2 * j + 1) * SLOT, 16384, 1024);
        reg_fence(o);
        wg_fence();
#pragma unroll
        for (int ks = 0; ks < 8; ks++)
          wgmma_n128_rs_tB(o, p[4 * ks], p[4 * ks + 1], p[4 * ks + 2], p[4 * ks + 3], db + ((ks * 2048) >> 4));
        wg_commit();
        wg_wait<0>();
        reg_fence(o);
        if (j != 13 && lane == 0) mbar_arrive(sb + OFF_EMPTY + (U_KV + 2 * j + 1) * 8);
      }
      if (j == 1 && warp == 7) {
        const int idx = 2 * hkv + r;
        uint4* z = reinterpret_cast<uint4*>(out + (size_t)(b * SQ + 2 * idx) * DM);
#pragma unroll
        for (int i = 0; i < 4; i++) z[i * 32 + lane] = make_uint4(0, 0, 0, 0);
        fence_async_all();
        __syncwarp();
        if (lane == 0) {
          __threadfence();
          const unsigned int old = atomicAdd(&g_zero_cnt[b * 32], 1u);
          zero_target = (old / 16 + 1) * 16;
        }
      }
    }

    if (w == 1) {
      if (warp == 7 && lane == 0) {
        int it = 0;
        unsigned int cur;
        do {
          asm volatile("ld.acquire.gpu.global.u32 %0, [%1];" : "=r"(cur) : "l"(&g_zero_cnt[b * 32]) : "memory");
          if (++it > SPIN_LIMIT) __trap();
        } while ((int)(cur - zero_target) < 0);
        fence_async_all();
      }
      bar_sync(3, 128);
      float4* dump = reinterpret_cast<float4*>(smem_raw + kv_slot(27) * SLOT);
#pragma unroll
      for (int i = 0; i < 16; i++) dump[i * 128 + t] = make_float4(o[4 * i], o[4 * i + 1], o[4 * i + 2], o[4 * i + 3]);
      *reinterpret_cast<float4*>(smem_raw + OFF_STATS + t * 16) = make_float4(m0, m1, l0, l1);
      bar_arrive(2, 256);
    } else {
      const int head = wi >> 1;
#pragma unroll
      for (int jj = 0; jj < 8; jj++) {
        const int j = 2 * jj + (mi >> 1), q = 16 * (wi & 1) + 8 * (mi & 1) + i8;
        const uint32_t addr = sb + OFF_O + head * 8192 + (j >> 3) * 4096 + q * 128 + (((j & 7) ^ i8) << 4);
        stsm4(addr, pack_bf16(o[8 * jj + 0], o[8 * jj + 1]), pack_bf16(o[8 * jj + 2], o[8 * jj + 3]),
              pack_bf16(o[8 * jj + 4], o[8 * jj + 5]), pack_bf16(o[8 * jj + 6], o[8 * jj + 7]));
      }
      fence_async_all();
    }
    bar_sync(1, 256);

    {
      float acc[4][16];
      auto issue = [&](int c, float (&d)[16]) {
        mbar_wait0(sb + OFF_FULL + (U_WO + c) * 8);
        const uint64_t da = mkdesc(sb + (c % 6) * SLOT + w * 16384, 16, 1024);
        const uint64_t db = mkdesc(sb + OFF_O + (c & 1) * 8192, 16, 1024);
        wg_fence();
#pragma unroll
        for (int ks = 0; ks < 8; ks++)
          wgmma_n32_tA(d, da + ((ks * 2048) >> 4), db + (((ks >> 2) * 4096 + (ks & 3) * 32) >> 4), ((c & 1) | ks) != 0);
        wg_commit();
      };
      auto release = [&](int c) { if (lane == 0) mbar_arrive(sb + OFF_EMPTY + (U_WO + c) * 8); };
      auto epilogue = [&](int cb, float (&d)[16]) {
        reg_fence(d);
        const uint32_t stg = sb + OFF_Q + (2 * w + (cb & 1)) * 4096;
        if (cb >= 2) {
          if (t == 0) asm volatile("cp.async.bulk.wait_group.read 1;" ::: "memory");
          bar_sync(3 + (w ^ 1), 128);
        }
#pragma unroll
        for (int jj = 0; jj < 2; jj++) {
          const int j = 2 * jj + (mi >> 1), c16 = 2 * wi + (mi & 1);
          stsm4t(stg + (8 * j + i8) * 128 + ((c16 ^ i8) << 4),
                 pack_bf16(d[8 * jj + 0], d[8 * jj + 1]), pack_bf16(d[8 * jj + 2], d[8 * jj + 3]),
                 pack_bf16(d[8 * jj + 4], d[8 * jj + 5]), pack_bf16(d[8 * jj + 6], d[8 * jj + 7]));
        }
        fence_async_smem();
        bar_sync(3 + (w ^ 1), 128);
        if (t == 0) {
          tma_reduce2d(&map_out, cb * 128 + w * 64, b * SQ, stg);
          asm volatile("cp.async.bulk.commit_group;" ::: "memory");
        }
      };
      issue(0, acc[0]); issue(1, acc[0]); issue(2, acc[1]);
      wg_wait<2>(); release(0);
      issue(3, acc[1]);
      wg_wait<2>(); release(1); epilogue(0, acc[0]);
      issue(4, acc[2]); issue(5, acc[2]);
      wg_wait<2>(); epilogue(1, acc[1]);
      issue(6, acc[3]); issue(7, acc[3]);
      wg_wait<2>(); epilogue(2, acc[2]);
      wg_wait<0>(); epilogue(3, acc[3]);
      if (t == 0) asm volatile("cp.async.bulk.wait_group.read 0;" ::: "memory");
    }
  }
}

typedef CUresult (*EncodeFn)(CUtensorMap*, CUtensorMapDataType, cuuint32_t, void*, const cuuint64_t*, const cuuint64_t*,
                             const cuuint32_t*, const cuuint32_t*, CUtensorMapInterleave, CUtensorMapSwizzle,
                             CUtensorMapL2promotion, CUtensorMapFloatOOBfill);

static bool encode(EncodeFn fn, CUtensorMap* m, int rank, const void* base, const cuuint64_t* dims, const cuuint64_t* strides,
                   const cuuint32_t* box) {
  const cuuint32_t es[3] = {1, 1, 1};
  return fn(m, CU_TENSOR_MAP_DATA_TYPE_BFLOAT16, (cuuint32_t)rank, const_cast<void*>(base), dims, strides, box, es,
            CU_TENSOR_MAP_INTERLEAVE_NONE, CU_TENSOR_MAP_SWIZZLE_128B, CU_TENSOR_MAP_L2_PROMOTION_L2_128B,
            CU_TENSOR_MAP_FLOAT_OOB_FILL_NONE) == CUDA_SUCCESS;
}

}

extern "C" void kernel_launch(void* const* d_in, const int* in_sizes, int n_in, void* d_out, int out_size) {
  using namespace sbk;
  (void)in_sizes; (void)n_in; (void)out_size;
  static EncodeFn fn = nullptr;
  if (!fn) {
    void* p = nullptr;
    cudaDriverEntryPointQueryResult q;
    if (cudaGetDriverEntryPoint("cuTensorMapEncodeTiled", &p, cudaEnableDefault, &q) != cudaSuccess || !p) return;
    fn = (EncodeFn)p;
    cudaFuncSetAttribute(fused_kernel, cudaFuncAttributeMaxDynamicSharedMemorySize, (int)SMEM_BYTES);
  }
  CUtensorMap mx, mwq, mk, mv, mwo, mo;
  bool ok = true;
  { const cuuint64_t d[3] = {64, NB * SQ, DM / 64}, s[2] = {DM * 2, 128}; const cuuint32_t bx[3] = {64, SQ, DM / 64};
    ok &= encode(fn, &mx, 3, d_in[0], d, s, bx); }
  { const cuuint64_t d[3] = {64, (cuuint64_t)NB * HKV * SK, 2}, s[2] = {DH * 2, 128}; const cuuint32_t bx[3] = {64, 128, 2};
    ok &= encode(fn, &mk, 3, d_in[1], d, s, bx);
    ok &= encode(fn, &mv, 3, d_in[2], d, s, bx); }
  { const cuuint64_t d[3] = {64, DM, HQ * DH / 64}, s[2] = {HQ * DH * 2, 128}; const cuuint32_t bx[3] = {64, 64, 4};
    ok &= encode(fn, &mwq, 3, d_in[3], d, s, bx); }
  { const cuuint64_t d[3] = {64, HQ * DH, DM / 64}, s[2] = {DM * 2, 128}; const cuuint32_t bx[3] = {64, 128, 2};
    ok &= encode(fn, &mwo, 3, d_in[4], d, s, bx); }
  { const cuuint64_t d[2] = {DM, NB * SQ}, s[1] = {DM * 2}; const cuuint32_t bx[2] = {64, SQ};
    ok &= encode(fn, &mo, 2, d_out, d, s, bx); }
  if (!ok) return;
  fused_kernel<<<128, NTHREADS, SMEM_BYTES, cudaStreamPerThread>>>(mx, mwq, mk, mv, mwo, mo, (__nv_bfloat16*)d_out);
}
```

```cpp
#include <cuda_runtime.h>
#include <cuda_bf16.h>
#include <cuda.h>
#include <stdint.h>

namespace sbk {

constexpr int NB = 8, SQ = 32, DM = 512, HQ = 32, HKV = 8, SK = 8192, DH = 128, WIN = 2048;
constexpr int NT = WIN / 128;
constexpr uint32_t SLOT = 32768;
constexpr uint32_t OFF_AUX = 6 * SLOT;
constexpr uint32_t OFF_Q = OFF_AUX;
constexpr uint32_t OFF_MISC = OFF_AUX + 32768;
constexpr uint32_t OFF_FULL = OFF_MISC;
constexpr uint32_t OFF_EMPTY = OFF_MISC + 96;
constexpr uint32_t OFF_XFULL = OFF_MISC + 144;
constexpr uint32_t OFF_ZOK = OFF_MISC + 152;
constexpr uint32_t OFF_STATS = OFF_MISC + 1024;
constexpr uint32_t SMEM_BYTES = OFF_MISC + 3072;
constexpr int NTHREADS = 352;
constexpr int PACE_T0 = 650;
constexpr int PACE_D = 680;
constexpr int PACE_LAG = 680;
constexpr int LAG2_FROM = 30;
constexpr int PACE_LAG2 = 400;
constexpr int RED_FROM = 1;
static_assert(RED_FROM == 1, "one staging buffer per reduction kind");
constexpr int XCH_AT = 2;
constexpr int MERGE_PF = 8;
constexpr int SPIN_LIMIT = 1 << 24;

__device__ unsigned int g_zero_cnt[NB * 32];

__device__ __forceinline__ void mbar_init(uint32_t bar, uint32_t cnt) {
  asm volatile("mbarrier.init.shared::cta.b64 [%0], %1;" ::"r"(bar), "r"(cnt) : "memory");
}
__device__ __forceinline__ void mbar_expect_tx(uint32_t bar, uint32_t bytes) {
  asm volatile("mbarrier.arrive.expect_tx.shared::cta.b64 _, [%0], %1;" ::"r"(bar), "r"(bytes) : "memory");
}
__device__ __forceinline__ void mbar_arrive(uint32_t bar) {
  asm volatile("mbarrier.arrive.shared::cta.b64 _, [%0];" ::"r"(bar) : "memory");
}
__device__ __forceinline__ bool mbar_try(uint32_t bar, uint32_t parity) {
  uint32_t ok;
  asm volatile("{\n.reg .pred p;\nmbarrier.try_wait.parity.shared::cta.b64 p, [%1], %2;\nselp.u32 %0,1,0,p;\n}"
               : "=r"(ok) : "r"(bar), "r"(parity) : "memory");
  return ok;
}
__device__ __forceinline__ void mbar_wait(uint32_t bar, uint32_t parity) {
  int it = 0;
  while (!mbar_try(bar, parity)) { if (++it > SPIN_LIMIT) __trap(); }
}
__device__ __forceinline__ uint32_t now_ns() { uint32_t t; asm volatile("mov.u32 %0, %%globaltimer_lo;" : "=r"(t)); return t; }
__device__ __forceinline__ void wait_until(uint32_t t0, int due) {
  int it = 0;
  while ((int)(now_ns() - t0) < due && ++it < SPIN_LIMIT) {}
}
__device__ __forceinline__ void tma3d(uint32_t dst, const CUtensorMap* m, int c0, int c1, int c2, uint32_t bar) {
  asm volatile("cp.async.bulk.tensor.3d.shared::cluster.global.mbarrier::complete_tx::bytes [%0], [%1, {%3, %4, %5}], [%2];"
               ::"r"(dst), "l"(m), "r"(bar), "r"(c0), "r"(c1), "r"(c2) : "memory");
}
__device__ __forceinline__ void tma_kv(uint32_t dst, const CUtensorMap* m, int row, uint32_t bar) {
  asm volatile("cp.async.bulk.tensor.4d.shared::cluster.global.mbarrier::complete_tx::bytes [%0], [%1, {%3, %3, %3, %4}], [%2];"
               ::"r"(dst), "l"(m), "r"(bar), "r"(0), "r"(row >> 3) : "memory");
}
__device__ __forceinline__ void bulk_prefetch(const void* p, uint32_t bytes) {
  asm volatile("cp.async.bulk.prefetch.L2.global [%0], %1;" ::"l"(p), "r"(bytes) : "memory");
}
__device__ __forceinline__ void tma5d(uint32_t dst, const CUtensorMap* m, int c3, int c4, uint32_t bar) {
  asm volatile("cp.async.bulk.tensor.5d.shared::cluster.global.mbarrier::complete_tx::bytes [%0], [%1, {%3, %3, %3, %4, %5}], [%2];"
               ::"r"(dst), "l"(m), "r"(bar), "r"(0), "r"(c3), "r"(c4) : "memory");
}
__device__ __forceinline__ void tma_reduce2d(const CUtensorMap* m, int c0, int c1, uint32_t src) {
  asm volatile("cp.reduce.async.bulk.tensor.2d.global.shared::cta.add.tile.bulk_group [%0, {%2, %3}], [%1];"
               ::"l"(m), "r"(src), "r"(c0), "r"(c1) : "memory");
}
__device__ __forceinline__ void red_add_bf16x8(void* gptr, uint4 v) {
  asm volatile("red.global.add.noftz.v4.bf16x2 [%0], {%1, %2, %3, %4};" ::"l"(gptr), "r"(v.x), "r"(v.y), "r"(v.z), "r"(v.w) : "memory");
}
__device__ __forceinline__ uint4 lds128(uint32_t addr) {
  uint4 v; asm volatile("ld.shared.v4.u32 {%0, %1, %2, %3}, [%4];" : "=r"(v.x), "=r"(v.y), "=r"(v.z), "=r"(v.w) : "r"(addr) : "memory"); return v;
}
__device__ __forceinline__ void bar_sync(int id, int n) { asm volatile("bar.sync %0, %1;" ::"r"(id), "r"(n) : "memory"); }
__device__ __forceinline__ void bar_arrive(int id, int n) { asm volatile("bar.arrive %0, %1;" ::"r"(id), "r"(n) : "memory"); }
__device__ __forceinline__ void fence_async_smem() { asm volatile("fence.proxy.async.shared::cta;" ::: "memory"); }
__device__ __forceinline__ void fence_async_all() { asm volatile("fence.proxy.async;" ::: "memory"); }
__device__ __forceinline__ void wg_fence() { asm volatile("wgmma.fence.sync.aligned;" ::: "memory"); }
__device__ __forceinline__ void wg_commit() { asm volatile("wgmma.commit_group.sync.aligned;" ::: "memory"); }
template <int N> __device__ __forceinline__ void wg_wait() { asm volatile("wgmma.wait_group.sync.aligned %0;" ::"n"(N) : "memory"); }
template <int N> __device__ __forceinline__ void reg_fence(float (&d)[N]) {
#pragma unroll
  for (int i = 0; i < N; i++) asm volatile("" : "+f"(d[i])::"memory");
}
__device__ __forceinline__ uint64_t mkdesc(uint32_t addr, uint32_t lbo, uint32_t sbo) {
  return (uint64_t)((addr >> 4) & 0x3FFF) | ((uint64_t)(lbo >> 4) << 16) | ((uint64_t)(sbo >> 4) << 32) | (1ull << 62);
}
__device__ __forceinline__ float ex2(float x) { float y; asm("ex2.approx.ftz.f32 %0, %1;" : "=f"(y) : "f"(x)); return y; }
__device__ __forceinline__ uint32_t pack_bf16(float lo, float hi) {
  uint32_t r; asm("cvt.rn.bf16x2.f32 %0, %1, %2;" : "=r"(r) : "f"(hi), "f"(lo)); return r;
}
__device__ __forceinline__ void stsm4(uint32_t addr, uint32_t a, uint32_t b, uint32_t c, uint32_t d) {
  asm volatile("stmatrix.sync.aligned.m8n8.x4.shared.b16 [%0], {%1,%2,%3,%4};" ::"r"(addr), "r"(a), "r"(b), "r"(c), "r"(d) : "memory");
}
__device__ __forceinline__ void stsm4t(uint32_t addr, uint32_t a, uint32_t b, uint32_t c, uint32_t d) {
  asm volatile("stmatrix.sync.aligned.m8n8.x4.trans.shared.b16 [%0], {%1,%2,%3,%4};" ::"r"(addr), "r"(a), "r"(b), "r"(c), "r"(d) : "memory");
}

#define ACC16(d) "+f"(d[0]), "+f"(d[1]), "+f"(d[2]), "+f"(d[3]), "+f"(d[4]), "+f"(d[5]), "+f"(d[6]), "+f"(d[7]), \
                 "+f"(d[8]), "+f"(d[9]), "+f"(d[10]), "+f"(d[11]), "+f"(d[12]), "+f"(d[13]), "+f"(d[14]), "+f"(d[15])
#define ACC64(d) ACC16(d), \
  "+f"(d[16]), "+f"(d[17]), "+f"(d[18]), "+f"(d[19]), "+f"(d[20]), "+f"(d[21]), "+f"(d[22]), "+f"(d[23]), \
  "+f"(d[24]), "+f"(d[25]), "+f"(d[26]), "+f"(d[27]), "+f"(d[28]), "+f"(d[29]), "+f"(d[30]), "+f"(d[31]), \
  "+f"(d[32]), "+f"(d[33]), "+f"(d[34]), "+f"(d[35]), "+f"(d[36]), "+f"(d[37]), "+f"(d[38]), "+f"(d[39]), \
  "+f"(d[40]), "+f"(d[41]), "+f"(d[42]), "+f"(d[43]), "+f"(d[44]), "+f"(d[45]), "+f"(d[46]), "+f"(d[47]), \
  "+f"(d[48]), "+f"(d[49]), "+f"(d[50]), "+f"(d[51]), "+f"(d[52]), "+f"(d[53]), "+f"(d[54]), "+f"(d[55]), \
  "+f"(d[56]), "+f"(d[57]), "+f"(d[58]), "+f"(d[59]), "+f"(d[60]), "+f"(d[61]), "+f"(d[62]), "+f"(d[63])
#define ACC32(d) ACC16(d), \
  "+f"(d[16]), "+f"(d[17]), "+f"(d[18]), "+f"(d[19]), "+f"(d[20]), "+f"(d[21]), "+f"(d[22]), "+f"(d[23]), \
  "+f"(d[24]), "+f"(d[25]), "+f"(d[26]), "+f"(d[27]), "+f"(d[28]), "+f"(d[29]), "+f"(d[30]), "+f"(d[31])
#define REGS32 "{%0,%1,%2,%3,%4,%5,%6,%7,%8,%9,%10,%11,%12,%13,%14,%15,%16,%17,%18,%19,%20,%21,%22,%23,%24,%25,%26,%27,%28,%29,%30,%31}"
#define REGS16 "{%0,%1,%2,%3,%4,%5,%6,%7,%8,%9,%10,%11,%12,%13,%14,%15}"
#define REGS64 "{%0,%1,%2,%3,%4,%5,%6,%7,%8,%9,%10,%11,%12,%13,%14,%15,%16,%17,%18,%19,%20,%21,%22,%23,%24,%25,%26,%27,%28,%29,%30,%31," \
               "%32,%33,%34,%35,%36,%37,%38,%39,%40,%41,%42,%43,%44,%45,%46,%47,%48,%49,%50,%51,%52,%53,%54,%55,%56,%57,%58,%59,%60,%61,%62,%63}"

__device__ __forceinline__ void wgmma_n32_tA(float (&d)[16], uint64_t da, uint64_t db, int acc) {
  asm volatile("{\n.reg .pred p;\nsetp.ne.b32 p, %18, 0;\n"
               "wgmma.mma_async.sync.aligned.m64n32k16.f32.bf16.bf16 " REGS16 ", %16, %17, p, 1, 1, 1, 0;\n}"
               : ACC16(d) : "l"(da), "l"(db), "r"(acc));
}
__device__ __forceinline__ void wgmma_n128_ss(float (&d)[64], uint64_t da, uint64_t db, int acc) {
  asm volatile("{\n.reg .pred p;\nsetp.ne.b32 p, %66, 0;\n"
               "wgmma.mma_async.sync.aligned.m64n128k16.f32.bf16.bf16 " REGS64 ", %64, %65, p, 1, 1, 0, 0;\n}"
               : ACC64(d) : "l"(da), "l"(db), "r"(acc));
}
__device__ __forceinline__ void wgmma_n128_rs_tB(float (&d)[64], uint32_t a0, uint32_t a1, uint32_t a2, uint32_t a3, uint64_t db) {
  asm volatile("{\n.reg .pred p;\nsetp.ne.b32 p, 1, 0;\n"
               "wgmma.mma_async.sync.aligned.m64n128k16.f32.bf16.bf16 " REGS64 ", {%64,%65,%66,%67}, %68, p, 1, 1, 1;\n}"
               : ACC64(d) : "r"(a0), "r"(a1), "r"(a2), "r"(a3), "l"(db));
}

__device__ __forceinline__ void wgmma_sp_n64(float (&d)[32], uint32_t a0, uint32_t a1, uint32_t a2, uint32_t a3, uint64_t db, int acc) {
  asm volatile("{\n.reg .pred p;\nsetp.ne.b32 p, %38, 0;\n"
               "wgmma.mma_async.sp.sync.aligned.m64n64k32.f32.bf16.bf16 " REGS32 ", {%32,%33,%34,%35}, %36, %37, 0, p, 1, 1, 1;\n}"
               : ACC32(d) : "r"(a0), "r"(a1), "r"(a2), "r"(a3), "l"(db), "r"(0xEEEE4444u), "r"(acc));
}

__device__ __forceinline__ int item_k(int j) { return j == 0 ? 0 : 2 * j - 1; }
__device__ __forceinline__ int item_v(int j) { return j == NT - 1 ? 31 : 2 * j + 2; }
__device__ __forceinline__ uint32_t pos_slot(int p) {
  return (uint32_t)((p + 4) % 6);
}
__device__ __forceinline__ uint32_t pos_use(int p) {
  const int s = (p + 4) % 6; return (uint32_t)((p + 4) / 6 + (s < 4 ? 1 : 0));
}
__device__ __forceinline__ uint32_t full_bar(uint32_t sb, uint32_t slot, uint32_t use) { return sb + OFF_FULL + ((use & 1) * 6 + slot) * 8; }
__device__ __forceinline__ void wait_full(uint32_t sb, uint32_t slot, uint32_t use) { mbar_wait(full_bar(sb, slot, use), (use >> 1) & 1); }
__device__ __forceinline__ void wait_empty(uint32_t sb, uint32_t slot, uint32_t use) { mbar_wait(sb + OFF_EMPTY + slot * 8, use & 1); }
__device__ __forceinline__ void map_cluster(int cl, int& b, int& hkv) {
  hkv = cl >> 3; b = cl & 7;
}

__global__ void
__launch_bounds__(NTHREADS, 1)
fused_kernel(const __grid_constant__ CUtensorMap map_x, const __grid_constant__ CUtensorMap map_wq,
             const __grid_constant__ CUtensorMap map_k, const __grid_constant__ CUtensorMap map_v,
             const __grid_constant__ CUtensorMap map_wo, const __grid_constant__ CUtensorMap map_out,
             __nv_bfloat16* __restrict__ out, const __nv_bfloat16* __restrict__ kptr, const __nv_bfloat16* __restrict__ vptr,
             const __nv_bfloat16* __restrict__ qptr) {
  extern __shared__ __align__(1024) unsigned char smem_raw[];
  const uint32_t sb = (uint32_t)__cvta_generic_to_shared(smem_raw);
  const int tid = threadIdx.x, lane = tid & 31;
  const int warp = __shfl_sync(0xffffffffu, tid >> 5, 0);
  const int cl = blockIdx.x >> 1;
  int r = blockIdx.x & 1;
  int hkv, b;
  map_cluster(cl, b, hkv);
  const int head0 = 4 * hkv + 2 * r;
  const int crot = 2 * hkv + r;
  const int kvrow = (b * HKV + hkv) * SK + (SK - WIN);

  const uint32_t t0_ns = now_ns();
  auto kv_row = [&](int i, bool& isv) {
    int j;
    if (i == 0) { j = 0; isv = false; } else if (i == 31) { j = NT - 1; isv = true; }
    else if (i & 1) { j = (i + 1) >> 1; isv = false; } else { j = (i - 2) >> 1; isv = true; }
    return kvrow + j * 128;
  };
  constexpr int t_sched = PACE_T0;
  if (warp == 0) bulk_prefetch(qptr + (size_t)(256 + b * 32 + lane) * (HQ * DH) + head0 * DH, 512);
  if (lane == 0) {
    if (warp == 8) {
#pragma unroll 1
      for (int i = 0; i < 5; i++) {
        const uint32_t slot = i == 0 ? 6 : i - 1;
        const uint32_t bar = i == 0 ? sb + OFF_XFULL : sb + OFF_FULL + slot * 8;
        mbar_init(bar, 1);
        asm volatile("fence.mbarrier_init.release.cluster;" ::: "memory");
        mbar_expect_tx(bar, SLOT);
        const CUtensorMap* m = i == 0 ? &map_x : &map_wq;
        const int c1 = i == 0 ? b * SQ : (i - 1) * 64;
        const int c2 = i == 0 ? 0 : head0 * 2;
        tma3d(sb + slot * SLOT, m, 0, c1, c2, bar);
      }
    } else if (warp < 6) {
      mbar_init(sb + OFF_FULL + (6 + warp) * 8, 1);
      mbar_init(sb + OFF_EMPTY + warp * 8, 8);
    } else if (warp == 9) {
      mbar_init(sb + OFF_ZOK, 1);
      if (sb & 1023) __trap();
    } else if (warp == 10) {
      bulk_prefetch(kptr + (size_t)kvrow * DH + r * 4096, 8192);
      mbar_init(sb + OFF_FULL + 4 * 8, 1);
      mbar_init(sb + OFF_FULL + 5 * 8, 1);
    }
    asm volatile("fence.mbarrier_init.release.cluster;" ::: "memory");
  }
  __syncthreads();

  if (warp == 8) {
    if (lane == 0) {
#pragma unroll 1
      for (int kc = 4; kc < 8; kc++) {
        wait_empty(sb, kc - 4, 0);
        const uint32_t bar = full_bar(sb, kc - 4, 1);
        mbar_expect_tx(bar, SLOT);
        tma3d(sb + (kc - 4) * SLOT, &map_wq, 0, kc * 64, head0 * 2, bar);
      }
#pragma unroll 1
      for (int p = 2; p < 40; p++) {
        const uint32_t slot = pos_slot(p), use = pos_use(p);
        if (p < 32) wait_until(t0_ns, t_sched + p * PACE_D + (p < LAG2_FROM ? PACE_LAG : PACE_LAG2));
        wait_empty(sb, slot, use - 1);
        const uint32_t bar = full_bar(sb, slot, use);
        mbar_expect_tx(bar, SLOT);
        if (p < 32) {
          bool isv; const int row = kv_row(p, isv);
          tma_kv(sb + slot * SLOT, isv ? &map_v : &map_k, row, bar);
        } else {
          tma5d(sb + slot * SLOT, &map_wo, head0 * (DH / 2), (p - 32 + crot) & 7, bar);
        }
      }
    }
  } else if (warp == 10) {
    if (lane == 0) {
#pragma unroll 1
      for (int p = 0; p < 32; p++) {
        wait_until(t0_ns, t_sched + p * PACE_D);
        bool isv; const int row = kv_row(p, isv);
        if (p < 2) {
          const uint32_t bar = sb + OFF_FULL + (4 + p) * 8;
          mbar_expect_tx(bar, SLOT);
          tma_kv(sb + (4 + p) * SLOT, &map_k, row, bar);
        } else if ((p & 1) == r) {
          bulk_prefetch((isv ? vptr : kptr) + (size_t)row * DH, SLOT);
        }
      }
    }
  } else if (warp == 9) {
    const int idx = 2 * hkv + r;
    uint4* z = reinterpret_cast<uint4*>(out + (size_t)(b * SQ + 2 * idx) * DM);
#pragma unroll
    for (int i = 0; i < 4; i++) z[i * 32 + lane] = make_uint4(0, 0, 0, 0);
    fence_async_all();
    __syncwarp();
    if (lane == 0) {
      __threadfence();
      const unsigned int old = atomicAdd(&g_zero_cnt[b * 32], 1u);
      const unsigned int target = (old / 16 + 1) * 16;
      int it = 0;
      unsigned int cur;
      while (true) {
        asm volatile("ld.acquire.gpu.global.u32 %0, [%1];" : "=r"(cur) : "l"(&g_zero_cnt[b * 32]) : "memory");
        if ((int)(cur - target) >= 0) break;
        if (++it > SPIN_LIMIT) __trap();
        __nanosleep(200);
      }
      fence_async_all();
      mbar_arrive(sb + OFF_ZOK);
    }
  } else {
    const int w = warp >> 2, wi = warp & 3, t = tid & 127;
    const int i8 = lane & 7, mi = lane >> 3;

    {
      float qa[2][16];
      mbar_wait(sb + OFF_XFULL, 0);
#pragma unroll 1
      for (int kc = 0; kc < 8; kc++) {
        wait_full(sb, kc & 3, kc >> 2);
        const uint64_t da = mkdesc(sb + (kc & 3) * SLOT + 2 * w * 8192, 16, 1024);
        const uint64_t db = mkdesc(sb + OFF_AUX + kc * 4096, 16, 1024);
        wg_fence();
#pragma unroll
        for (int mt = 0; mt < 2; mt++)
#pragma unroll
          for (int ks = 0; ks < 4; ks++)
            wgmma_n32_tA(qa[mt], da + ((mt * 8192 + ks * 2048) >> 4), db + ((ks * 32) >> 4), (kc | ks) != 0);
        wg_commit();
        wg_wait<0>();
        if (lane == 0) mbar_arrive(sb + OFF_EMPTY + (kc & 3) * 8);
      }
      reg_fence(qa[0]); reg_fence(qa[1]);
      bar_sync(1, 256);
#pragma unroll
      for (int mt = 0; mt < 2; mt++)
#pragma unroll
        for (int jj = 0; jj < 2; jj++) {
          const int j = 2 * jj + (mi >> 1), c16 = 2 * wi + (mi & 1);
          const uint32_t addr = sb + OFF_Q + mt * 8192 + (16 * j + 8 * w + i8) * 128 + ((c16 ^ i8) << 4);
          stsm4t(addr, pack_bf16(qa[mt][8 * jj + 0], qa[mt][8 * jj + 1]), pack_bf16(qa[mt][8 * jj + 2], qa[mt][8 * jj + 3]),
                 pack_bf16(qa[mt][8 * jj + 4], qa[mt][8 * jj + 5]), pack_bf16(qa[mt][8 * jj + 6], qa[mt][8 * jj + 7]));
        }
      fence_async_smem();
      bar_sync(1, 256);
    }

    const float cs = 0.08838834764831845f * 1.4426950408889634f;
    float o[64];
#pragma unroll
    for (int i = 0; i < 64; i++) o[i] = 0.f;
    float m0 = -INFINITY, m1 = -INFINITY, l0 = 0.f, l1 = 0.f;
    float2* stats = reinterpret_cast<float2*>(smem_raw + OFF_STATS);
    float4* dump = reinterpret_cast<float4*>(smem_raw + OFF_AUX);
    const int row0 = 16 * wi + (lane >> 2);
#pragma unroll 1
    for (int it = 0;; it++) {
      const int j = 2 * it + w;
      const bool last = (it == 7);
      const int ik = item_k(j), iv = item_v(j);
      float s[64];
      {
        wait_full(sb, pos_slot(ik), pos_use(ik));
        const uint64_t da = mkdesc(sb + OFF_Q, 16, 1024);
        const uint64_t db = mkdesc(sb + pos_slot(ik) * SLOT, 16, 2048);
        if (j == 1) bar_sync(7, 256);
        wg_fence();
#pragma unroll
        for (int ks = 0; ks < 8; ks++)
          wgmma_n128_ss(s, da + (((ks >> 2) * 8192 + (ks & 3) * 32) >> 4), db + (((ks >> 2) * 1024 + (ks & 3) * 32) >> 4), ks != 0);
        wg_commit();
        wg_wait<0>();
        reg_fence(s);
        if (j == 0) bar_arrive(7, 256);
        if (lane < 2) mbar_arrive(sb + OFF_EMPTY + pos_slot(ik) * 8);
      }
      float x0 = fmaxf(s[0], s[1]), x1 = fmaxf(s[2], s[3]);
#pragma unroll
      for (int i = 1; i < 16; i++) {
        x0 = fmaxf(x0, fmaxf(s[4 * i], s[4 * i + 1]));
        x1 = fmaxf(x1, fmaxf(s[4 * i + 2], s[4 * i + 3]));
      }
      x0 = fmaxf(x0, __shfl_xor_sync(0xffffffffu, x0, 1));
      x1 = fmaxf(x1, __shfl_xor_sync(0xffffffffu, x1, 1));
      x0 = fmaxf(x0, __shfl_xor_sync(0xffffffffu, x0, 2));
      x1 = fmaxf(x1, __shfl_xor_sync(0xffffffffu, x1, 2));
      const float n0 = fmaxf(m0, x0), n1 = fmaxf(m1, x1);
      float a0 = ex2((m0 - n0) * cs), a1 = ex2((m1 - n1) * cs);
      m0 = n0; m1 = n1;
      const float nb0 = -n0 * cs, nb1 = -n1 * cs;
      float r0 = 0.f, r1 = 0.f;
#pragma unroll
      for (int i = 0; i < 16; i++) {
        s[4 * i + 0] = ex2(fmaf(s[4 * i + 0], cs, nb0));
        s[4 * i + 1] = ex2(fmaf(s[4 * i + 1], cs, nb0));
        s[4 * i + 2] = ex2(fmaf(s[4 * i + 2], cs, nb1));
        s[4 * i + 3] = ex2(fmaf(s[4 * i + 3], cs, nb1));
        r0 += s[4 * i] + s[4 * i + 1];
        r1 += s[4 * i + 2] + s[4 * i + 3];
      }
      l0 = l0 * a0 + r0;
      l1 = l1 * a1 + r1;
      if (last) {
        l0 += __shfl_xor_sync(0xffffffffu, l0, 1); l1 += __shfl_xor_sync(0xffffffffu, l1, 1);
        l0 += __shfl_xor_sync(0xffffffffu, l0, 2); l1 += __shfl_xor_sync(0xffffffffu, l1, 2);
        if ((lane & 3) == 0) { stats[w * 64 + row0] = make_float2(m0, l0); stats[w * 64 + row0 + 8] = make_float2(m1, l1); }
        if (w == 0) {
          bar_arrive(5, 256);
        } else {
          bar_arrive(6, 256);
        }
      }
#pragma unroll
      for (int i = 0; i < 16; i++) { o[4 * i] *= a0; o[4 * i + 1] *= a0; o[4 * i + 2] *= a1; o[4 * i + 3] *= a1; }
      uint32_t p[32];
#pragma unroll
      for (int i = 0; i < 32; i++) p[i] = pack_bf16(s[2 * i], s[2 * i + 1]);
      {
        wait_full(sb, pos_slot(iv), pos_use(iv));
        const uint64_t db = mkdesc(sb + pos_slot(iv) * SLOT, 1024, 2048);
        reg_fence(o);
        wg_fence();
#pragma unroll
        for (int ks = 0; ks < 8; ks++)
          wgmma_n128_rs_tB(o, p[4 * ks], p[4 * ks + 1], p[4 * ks + 2], p[4 * ks + 3], db + ((ks * 4096) >> 4));
        wg_commit();
        if (last) break;
        wg_wait<0>();
        reg_fence(o);
        if (lane < 2) mbar_arrive(sb + OFF_EMPTY + pos_slot(iv) * 8);
      }
    }

    uint32_t of[32];
    float acc[2][32];
    uint4* xch = reinterpret_cast<uint4*>(smem_raw + OFF_AUX);
    auto chunk = [&](int cc) { return 2 * cc + (w ^ 1); };
    auto mma = [&](int cc, float (&d)[32], int ks0, int ks1) {
      const int c = chunk(cc);
      const uint64_t db = mkdesc(sb + pos_slot(32 + c) * SLOT, 16, 1024);
#pragma unroll
      for (int ks = ks0; ks < ks1; ks++)
        wgmma_sp_n64(d, of[4 * ks], of[4 * ks + 1], of[4 * ks + 2], of[4 * ks + 3], db + ((ks * 4096) >> 4), ks != 0);
    };
    auto ready = [&](int cc) {
      const int c = chunk(cc);
      wait_full(sb, pos_slot(32 + c), pos_use(32 + c));
      wg_fence();
    };
    {
      if (w == 0) bar_sync(6, 256); else bar_sync(5, 256);
      const float2 u0 = stats[(w ^ 1) * 64 + row0], u1 = stats[(w ^ 1) * 64 + row0 + 8];
      const float f0 = fmaxf(m0, u0.x), f1 = fmaxf(m1, u1.x);
      const float e0 = ex2((m0 - f0) * cs), e1 = ex2((m1 - f1) * cs);
      const float i0 = __fdividef(e0, l0 * e0 + u0.y * ex2((u0.x - f0) * cs));
      const float i1 = __fdividef(e1, l1 * e1 + u1.y * ex2((u1.x - f1) * cs));
      const uint32_t vbar = sb + OFF_EMPTY + pos_slot(item_v(14 + w)) * 8;
      if (w == 0) {
        wg_wait<0>();
        reg_fence(o);
        if (lane < 2) mbar_arrive(vbar);
#pragma unroll
        for (int i = 0; i < 16; i++)
          dump[i * 128 + t] = make_float4(o[4 * i] * i0, o[4 * i + 1] * i0, o[4 * i + 2] * i1, o[4 * i + 3] * i1);
        bar_arrive(2, 256);
        if (t == 0) mbar_wait(sb + OFF_ZOK, 0);
        bar_sync(1, 256);
#pragma unroll
        for (int i = 0; i < 8; i++) {
          const uint4 v = xch[i * 128 + t];
          of[4 * i] = v.x; of[4 * i + 1] = v.y; of[4 * i + 2] = v.z; of[4 * i + 3] = v.w;
        }
      } else {
        bar_sync(2, 256);
        float4 dv[MERGE_PF];
#pragma unroll
        for (int i = 0; i < MERGE_PF; i++) dv[i] = dump[i * 128 + t];
        wg_wait<0>();
        reg_fence(o);
        if (lane < 2) mbar_arrive(vbar);
#pragma unroll
        for (int i = 0; i < 16; i++) {
          const float4 v = i < MERGE_PF ? dv[i < MERGE_PF ? i : 0] : dump[i * 128 + t];
          of[2 * i] = pack_bf16(fmaf(o[4 * i], i0, v.x), fmaf(o[4 * i + 1], i0, v.y));
          of[2 * i + 1] = pack_bf16(fmaf(o[4 * i + 2], i1, v.z), fmaf(o[4 * i + 3], i1, v.w));
        }
      }
      ready(0); mma(0, acc[0], 0, XCH_AT);
      if (XCH_AT < 8) wg_commit();
      if (w == 1) {
#pragma unroll
        for (int i = 0; i < 8; i++) xch[i * 128 + t] = make_uint4(of[4 * i], of[4 * i + 1], of[4 * i + 2], of[4 * i + 3]);
        bar_sync(1, 256);
      }
      mma(0, acc[0], XCH_AT, 8); wg_commit();
    }

    {
      auto release = [&](int cc) { if (lane < 2) mbar_arrive(sb + OFF_EMPTY + pos_slot(32 + chunk(cc)) * 8); };
      auto epi = [&](int cc, float (&d)[32], int part) {
        const int c = (chunk(cc) + crot) & 7;
        const bool red = cc >= RED_FROM;
        const uint32_t stg = sb + OFF_AUX + 16384 + ((2 * w + (red ? 1 : 0)) * 4 + wi) * 1024;
        if (part == 0) {
          reg_fence(d);
          if (cc > RED_FROM) __syncwarp();
        }
        if (part < 2) {
          const int jj = part, j = 4 * jj + mi;
          stsm4(stg + i8 * 128 + ((j ^ i8) << 4),
                pack_bf16(d[16 * jj + 0] + d[16 * jj + 2], d[16 * jj + 1] + d[16 * jj + 3]),
                pack_bf16(d[16 * jj + 4] + d[16 * jj + 6], d[16 * jj + 5] + d[16 * jj + 7]),
                pack_bf16(d[16 * jj + 8] + d[16 * jj + 10], d[16 * jj + 9] + d[16 * jj + 11]),
                pack_bf16(d[16 * jj + 12] + d[16 * jj + 14], d[16 * jj + 13] + d[16 * jj + 15]));
        } else {
          if (red) {
            __syncwarp();
#pragma unroll
            for (int h = 0; h < 2; h++) {
              const int row = 4 * h + mi;
              const uint4 v = lds128(stg + row * 128 + ((i8 ^ row) << 4));
              red_add_bf16x8(out + (size_t)(b * SQ + 8 * wi + row) * DM + c * 64 + i8 * 8, v);
            }
          } else {
            fence_async_smem();
            __syncwarp();
            if (lane == 0) {
              tma_reduce2d(&map_out, c * 64, b * SQ + 8 * wi, stg);
              asm volatile("cp.async.bulk.commit_group;" ::: "memory");
            }
          }
        }
      };
      auto epilogue = [&](int cc, float (&d)[32]) { epi(cc, d, 0); epi(cc, d, 1); epi(cc, d, 2); };
      auto step = [&](int cc, float (&dprev)[32], float (&dnext)[32]) {
        ready(cc + 1); mma(cc + 1, dnext, 0, 2); wg_commit();
        wg_wait<1>();
        if (cc == 0) release(0);
        mma(cc + 1, dnext, 2, 4);
        epi(cc, dprev, 0);
        mma(cc + 1, dnext, 4, 6);
        epi(cc, dprev, 1);
        mma(cc + 1, dnext, 6, 8); wg_commit();
        epi(cc, dprev, 2);
      };
      step(0, acc[0], acc[1]);
      step(1, acc[1], acc[0]);
      wg_wait<0>();
      epilogue(2, acc[0]);
      ready(3); mma(3, acc[1], 0, 8); wg_commit();
      wg_wait<0>();
      epilogue(3, acc[1]);
      if (lane == 0) asm volatile("cp.async.bulk.wait_group.read 0;" ::: "memory");
    }
  }
}

typedef CUresult (*EncodeFn)(CUtensorMap*, CUtensorMapDataType, cuuint32_t, void*, const cuuint64_t*, const cuuint64_t*,
                             const cuuint32_t*, const cuuint32_t*, CUtensorMapInterleave, CUtensorMapSwizzle,
                             CUtensorMapL2promotion, CUtensorMapFloatOOBfill);

static bool encode(EncodeFn fn, CUtensorMap* m, int rank, const void* base, const cuuint64_t* dims, const cuuint64_t* strides,
                   const cuuint32_t* box) {
  const cuuint32_t es[5] = {1, 1, 1, 1, 1};
  return fn(m, CU_TENSOR_MAP_DATA_TYPE_BFLOAT16, (cuuint32_t)rank, const_cast<void*>(base), dims, strides, box, es,
            CU_TENSOR_MAP_INTERLEAVE_NONE, CU_TENSOR_MAP_SWIZZLE_128B,
            CU_TENSOR_MAP_L2_PROMOTION_L2_128B,
            CU_TENSOR_MAP_FLOAT_OOB_FILL_NONE) == CUDA_SUCCESS;
}

}

extern "C" void kernel_launch(void* const* d_in, const int* in_sizes, int n_in, void* d_out, int out_size) {
  using namespace sbk;
  (void)in_sizes; (void)n_in; (void)out_size;
  static EncodeFn fn = nullptr;
  if (!fn) {
    void* p = nullptr;
    cudaDriverEntryPointQueryResult q;
    if (cudaGetDriverEntryPoint("cuTensorMapEncodeTiled", &p, cudaEnableDefault, &q) != cudaSuccess || !p) return;
    fn = (EncodeFn)p;
    cudaFuncSetAttribute(fused_kernel, cudaFuncAttributeMaxDynamicSharedMemorySize, (int)SMEM_BYTES);
  }
  CUtensorMap mx, mwq, mk, mv, mwo, mo;
  bool ok = true;
  { const cuuint64_t d[3] = {64, NB * SQ, DM / 64}, s[2] = {DM * 2, 128}; const cuuint32_t bx[3] = {64, SQ, DM / 64};
    ok &= encode(fn, &mx, 3, d_in[0], d, s, bx); }
  { const cuuint64_t d[4] = {64, 8, 2, (cuuint64_t)NB * HKV * SK / 8}, s[3] = {DH * 2, 128, 8 * DH * 2};
    const cuuint32_t bx[4] = {64, 8, 2, 16};
    ok &= encode(fn, &mk, 4, d_in[1], d, s, bx);
    ok &= encode(fn, &mv, 4, d_in[2], d, s, bx); }
  { const cuuint64_t d[3] = {64, DM, HQ * DH / 64}, s[2] = {HQ * DH * 2, 128}; const cuuint32_t bx[3] = {64, 64, 4};
    ok &= encode(fn, &mwq, 3, d_in[3], d, s, bx); }
  { const cuuint64_t d[5] = {64, 2, 2, HQ * DH / 2, DM / 64}, s[4] = {DM * 2, DH * DM * 2, 2 * DM * 2, 128};
    const cuuint32_t bx[5] = {64, 2, 2, DH / 2, 1};
    ok &= encode(fn, &mwo, 5, d_in[4], d, s, bx); }
  { const cuuint64_t d[2] = {DM, NB * SQ}, s[1] = {DM * 2}; const cuuint32_t bx[2] = {64, 8};
    ok &= encode(fn, &mo, 2, d_out, d, s, bx); }
  if (!ok) return;
  fused_kernel<<<128, NTHREADS, SMEM_BYTES, cudaStreamPerThread>>>(mx, mwq, mk, mv, mwo, mo, (__nv_bfloat16*)d_out,
                                                                   (const __nv_bfloat16*)d_in[1], (const __nv_bfloat16*)d_in[2],
                                                                   (const __nv_bfloat16*)d_in[3]);
}
```
